```python
import torch

def _softmax(x, axis=-1):
    return torch.softmax(x, dim=axis)
def _gelu(x):
    return torch.nn.functional.gelu(x, approximate="tanh")
def _silu(x):
    return torch.nn.functional.silu(x)
def _sigmoid(x):
    return torch.sigmoid(x)
def _layernorm(x, axis=-1, eps=1e-5):
    m = x.mean(dim=axis, keepdim=True)
    v = x.var(dim=axis, keepdim=True, unbiased=False)
    return (x - m) / torch.sqrt(v + eps)
def _scatter_add(tgt, idx, src, axis=0):
    return tgt.clone().index_add_(axis, idx, src)
def _segment_sum(src, seg, n):
    out = torch.zeros((n,) + src.shape[1:], dtype=src.dtype)
    return out.index_add_(0, seg, src)
def _pad(x, pw):
    flat = tuple(v for pair in reversed(pw) for v in pair)
    return torch.nn.functional.pad(x, flat)

kernel_name = 'standalone__gqa_softmax__near_ridge'

def setup_inputs():

    _w = (lambda a: (lambda t: t.to(torch.bfloat16) if t.is_floating_point() else t)(torch.as_tensor(a)))
    B, Hq, Hkv, Sq, Sk, D = 16, 32, 4, 48, 1024, 128
    return {
        "q": _w((lambda *s: torch.randn(*s, dtype=torch.bfloat16) * 0.8)(B, Hq, Sq, D)),
        "k": _w((lambda *s: torch.randn(*s, dtype=torch.bfloat16) * 0.8)(B, Hkv, Sk, D)),
        "v": _w((lambda *s: torch.randn(*s, dtype=torch.bfloat16) * 0.05)(B, Hkv, Sk, D)),
    }

def reference(q, k, v):
    B, Hq, Sq, D = q.shape
    Hkv = k.shape[1]
    rep = Hq // Hkv
    k = (lambda x, n, axis: torch.repeat_interleave(x, n, dim=axis))(k, rep, axis=1)
    v = (lambda x, n, axis: torch.repeat_interleave(x, n, dim=axis))(v, rep, axis=1)
    scale = D ** -0.5
    scores = torch.einsum("bhqd,bhkd->bhqk", q, k) * scale
    p = _softmax(scores, axis=-1)
    return torch.einsum("bhqk,bhkd->bhqd", p, v)
```

```cpp
#include <cuda_runtime.h>
#include <cuda_bf16.h>
#include <cuda.h>
#include <stdint.h>

namespace {

constexpr int kD = 128;
constexpr int kSk = 1024;
constexpr int kRowsPerHead = 384;
constexpr int kNumKVHeads = 64;
constexpr int kBN = 128;
constexpr int kNumBlocks = kSk / kBN;
constexpr int kNumTiles = 2 * kNumBlocks;
constexpr int kStages = 5;
constexpr int kTileBytes = kBN * kD * 2;
constexpr int kQBytes = 64 * kD * 2;
constexpr int kSmemQ = 0;
constexpr int kSmemKV = 3 * kQBytes;
constexpr int kSmemBar = kSmemKV + kStages * kTileBytes;
constexpr int kSmemTotal = kSmemBar + 256 + 1280 + 1024;
constexpr int kThreads = 512;

#define LAZY 1
#define NPF 2
#define PACE 670
#define LEAD 300
#define SPLIT 6
#define B1 4
#define WAIT_LIMIT 2000000
#define DESC_FIRST 1
#define EPI 1
#define ORDER 1
#define PROF(slot) do {} while (0)
#define PROFG(slot) do {} while (0)
#define PROFL(slot) do {} while (0)
#define PROF_DUMP() do {} while (0)

__device__ __forceinline__ uint32_t smem_u32(const void* p) { return (uint32_t)__cvta_generic_to_shared(p); }

__device__ __forceinline__ void mbar_init(uint32_t bar, uint32_t count) {
    asm volatile("mbarrier.init.shared::cta.b64 [%0], %1;" :: "r"(bar), "r"(count) : "memory");
}
__device__ __forceinline__ void mbar_expect_tx(uint32_t bar, uint32_t bytes) {
    asm volatile("mbarrier.arrive.expect_tx.shared::cta.b64 _, [%0], %1;" :: "r"(bar), "r"(bytes) : "memory");
}
__device__ __forceinline__ bool mbar_try_wait(uint32_t bar) {
    uint32_t ok;
    asm volatile("{\n\t.reg .pred p;\n\t"
                 "mbarrier.try_wait.parity.shared::cta.b64 p, [%1], 0;\n\t"
                 "selp.u32 %0, 1, 0, p;\n\t}"
                 : "=r"(ok) : "r"(bar) : "memory");
    return ok != 0;
}
__device__ __forceinline__ void mbar_wait(uint32_t bar) {
    while (!mbar_try_wait(bar)) {}
}
__device__ __forceinline__ void mbar_wait_bounded(uint32_t bar) {
    for (int i = 0;; i++) {
        uint32_t ok;
        asm volatile("{\n\t.reg .pred p;\n\t"
                     "mbarrier.try_wait.parity.shared::cta.b64 p, [%1], 0, %2;\n\t"
                     "selp.u32 %0, 1, 0, p;\n\t}"
                     : "=r"(ok) : "r"(bar), "r"(1000000u) : "memory");
        if (ok) return;
        if (i > WAIT_LIMIT) __trap();
    }
}
__device__ __forceinline__ uint32_t map_to_cta(uint32_t addr, uint32_t cta) {
    uint32_t r; asm("mapa.shared::cluster.u32 %0, %1, %2;" : "=r"(r) : "r"(addr), "r"(cta)); return r;
}
__device__ __forceinline__ void mbar_arrive_cluster(uint32_t cluster_addr) {
    asm volatile("mbarrier.arrive.shared::cluster.b64 _, [%0];" :: "r"(cluster_addr) : "memory");
}
__device__ __forceinline__ void tma_load(uint32_t dst, const CUtensorMap* map, int group, uint32_t bar) {
    asm volatile("cp.async.bulk.tensor.4d.shared::cluster.global.mbarrier::complete_tx::bytes "
                 "[%0], [%1, {%4, %4, %4, %2}], [%3];"
                 :: "r"(dst), "l"(map), "r"(group), "r"(bar), "r"(0) : "memory");
}
__device__ __forceinline__ void tma_load_mc(uint32_t dst, const CUtensorMap* map, int group, uint32_t bar, uint16_t mask) {
    asm volatile("cp.async.bulk.tensor.4d.shared::cluster.global.mbarrier::complete_tx::bytes.multicast::cluster "
                 "[%0], [%1, {%5, %5, %5, %2}], [%3], %4;"
                 :: "r"(dst), "l"(map), "r"(group), "r"(bar), "h"(mask), "r"(0) : "memory");
}
__device__ __forceinline__ void tma_store(const CUtensorMap* map, int group, uint32_t src) {
    asm volatile("cp.async.bulk.tensor.4d.global.shared::cta.bulk_group [%0, {%3, %3, %3, %1}], [%2];"
                 :: "l"(map), "r"(group), "r"(src), "r"(0) : "memory");
}
__device__ __forceinline__ void l2_prefetch(const void* p) {
    asm volatile("cp.async.bulk.prefetch.L2.global [%0], 16384;" :: "l"(p) : "memory");
}
__device__ __forceinline__ void named_sync(int id) { asm volatile("bar.sync %0, 256;" :: "r"(id) : "memory"); }
__device__ __forceinline__ void named_arrive(int id) { asm volatile("bar.arrive %0, 256;" :: "r"(id) : "memory"); }

__device__ __forceinline__ void wgmma_fence() { asm volatile("wgmma.fence.sync.aligned;" ::: "memory"); }
__device__ __forceinline__ void wgmma_commit() { asm volatile("wgmma.commit_group.sync.aligned;" ::: "memory"); }
__device__ __forceinline__ void wgmma_wait0() { asm volatile("wgmma.wait_group.sync.aligned 0;" ::: "memory"); }

__device__ __forceinline__ uint64_t make_desc(uint32_t addr, uint32_t lbo, uint32_t sbo) {
    return (uint64_t)((addr & 0x3FFFF) >> 4) | ((uint64_t)(lbo >> 4) << 16) | ((uint64_t)(sbo >> 4) << 32) | (1ull << 62);
}

#define ACC64(d) \
    "+f"(d[0]), "+f"(d[1]), "+f"(d[2]), "+f"(d[3]), "+f"(d[4]), "+f"(d[5]), "+f"(d[6]), "+f"(d[7]), \
    "+f"(d[8]), "+f"(d[9]), "+f"(d[10]), "+f"(d[11]), "+f"(d[12]), "+f"(d[13]), "+f"(d[14]), "+f"(d[15]), \
    "+f"(d[16]), "+f"(d[17]), "+f"(d[18]), "+f"(d[19]), "+f"(d[20]), "+f"(d[21]), "+f"(d[22]), "+f"(d[23]), \
    "+f"(d[24]), "+f"(d[25]), "+f"(d[26]), "+f"(d[27]), "+f"(d[28]), "+f"(d[29]), "+f"(d[30]), "+f"(d[31]), \
    "+f"(d[32]), "+f"(d[33]), "+f"(d[34]), "+f"(d[35]), "+f"(d[36]), "+f"(d[37]), "+f"(d[38]), "+f"(d[39]), \
    "+f"(d[40]), "+f"(d[41]), "+f"(d[42]), "+f"(d[43]), "+f"(d[44]), "+f"(d[45]), "+f"(d[46]), "+f"(d[47]), \
    "+f"(d[48]), "+f"(d[49]), "+f"(d[50]), "+f"(d[51]), "+f"(d[52]), "+f"(d[53]), "+f"(d[54]), "+f"(d[55]), \
    "+f"(d[56]), "+f"(d[57]), "+f"(d[58]), "+f"(d[59]), "+f"(d[60]), "+f"(d[61]), "+f"(d[62]), "+f"(d[63])
#define OUT64(d) \
    "=f"(d[0]), "=f"(d[1]), "=f"(d[2]), "=f"(d[3]), "=f"(d[4]), "=f"(d[5]), "=f"(d[6]), "=f"(d[7]), \
    "=f"(d[8]), "=f"(d[9]), "=f"(d[10]), "=f"(d[11]), "=f"(d[12]), "=f"(d[13]), "=f"(d[14]), "=f"(d[15]), \
    "=f"(d[16]), "=f"(d[17]), "=f"(d[18]), "=f"(d[19]), "=f"(d[20]), "=f"(d[21]), "=f"(d[22]), "=f"(d[23]), \
    "=f"(d[24]), "=f"(d[25]), "=f"(d[26]), "=f"(d[27]), "=f"(d[28]), "=f"(d[29]), "=f"(d[30]), "=f"(d[31]), \
    "=f"(d[32]), "=f"(d[33]), "=f"(d[34]), "=f"(d[35]), "=f"(d[36]), "=f"(d[37]), "=f"(d[38]), "=f"(d[39]), \
    "=f"(d[40]), "=f"(d[41]), "=f"(d[42]), "=f"(d[43]), "=f"(d[44]), "=f"(d[45]), "=f"(d[46]), "=f"(d[47]), \
    "=f"(d[48]), "=f"(d[49]), "=f"(d[50]), "=f"(d[51]), "=f"(d[52]), "=f"(d[53]), "=f"(d[54]), "=f"(d[55]), \
    "=f"(d[56]), "=f"(d[57]), "=f"(d[58]), "=f"(d[59]), "=f"(d[60]), "=f"(d[61]), "=f"(d[62]), "=f"(d[63])
#define REGS64 \
    "{%0, %1, %2, %3, %4, %5, %6, %7, %8, %9, %10, %11, %12, %13, %14, %15, " \
    "%16, %17, %18, %19, %20, %21, %22, %23, %24, %25, %26, %27, %28, %29, %30, %31, " \
    "%32, %33, %34, %35, %36, %37, %38, %39, %40, %41, %42, %43, %44, %45, %46, %47, " \
    "%48, %49, %50, %51, %52, %53, %54, %55, %56, %57, %58, %59, %60, %61, %62, %63}"

__device__ __forceinline__ void wgmma_ss(float (&d)[64], uint64_t da, uint64_t db) {
    asm volatile("wgmma.mma_async.sync.aligned.m64n128k16.f32.bf16.bf16 " REGS64 ", %64, %65, 1, 1, 1, 0, 0;"
                 : ACC64(d) : "l"(da), "l"(db));
}
__device__ __forceinline__ void wgmma_ss_init(float (&d)[64], uint64_t da, uint64_t db) {
    asm volatile("wgmma.mma_async.sync.aligned.m64n128k16.f32.bf16.bf16 " REGS64 ", %64, %65, 0, 1, 1, 0, 0;"
                 : OUT64(d) : "l"(da), "l"(db));
}
__device__ __forceinline__ void wgmma_rs(float (&d)[64], uint32_t a0, uint32_t a1, uint32_t a2, uint32_t a3, uint64_t db) {
    asm volatile("wgmma.mma_async.sync.aligned.m64n128k16.f32.bf16.bf16 " REGS64 ", {%64, %65, %66, %67}, %68, 1, 1, 1, 1;"
                 : ACC64(d) : "r"(a0), "r"(a1), "r"(a2), "r"(a3), "l"(db));
}
__device__ __forceinline__ void fence_regs(float (&d)[64]) {
#pragma unroll
    for (int i = 0; i < 64; i++) asm volatile("" : "+f"(d[i]) :: "memory");
}
__device__ __forceinline__ float ex2(float x) { float y; asm("ex2.approx.ftz.f32 %0, %1;" : "=f"(y) : "f"(x)); return y; }
__device__ __forceinline__ float ex2_if(float x, uint32_t go) {
    asm("{\n\t.reg .pred p;\n\tsetp.ne.u32 p, %1, 0;\n\t@p ex2.approx.ftz.f32 %0, %0;\n\t}" : "+f"(x) : "r"(go));
    return x;
}
__device__ __forceinline__ uint32_t pack_bf16(float lo, float hi) {
    uint32_t r; asm("cvt.rn.bf16x2.f32 %0, %1, %2;" : "=r"(r) : "f"(hi), "f"(lo)); return r;
}

__device__ __forceinline__ float bf_lo(uint32_t v) { return __uint_as_float(v << 16); }
__device__ __forceinline__ float bf_hi(uint32_t v) { return __uint_as_float(v & 0xffff0000u); }

__device__ __forceinline__ void exact_row(const uint8_t* q, const uint8_t* k, const uint8_t* v, uint8_t* out, int lane) {
    const float c = 0.08838834764831845f * 1.4426950408889634f;
    const uint2 qq = *(const uint2*)(q + lane * 8);
    const float q0 = bf_lo(qq.x), q1 = bf_hi(qq.x), q2 = bf_lo(qq.y), q3 = bf_hi(qq.y);
    float m = -INFINITY, l = 0.f, a0 = 0.f, a1 = 0.f, a2 = 0.f, a3 = 0.f;
#pragma unroll 4
    for (int j = 0; j < kSk; j++) {
        const uint2 kk = *(const uint2*)(k + j * 256 + lane * 8);
        const uint2 vv = *(const uint2*)(v + j * 256 + lane * 8);
        float s = q0 * bf_lo(kk.x) + q1 * bf_hi(kk.x) + q2 * bf_lo(kk.y) + q3 * bf_hi(kk.y);
#pragma unroll
        for (int d = 16; d > 0; d >>= 1) s += __shfl_xor_sync(0xffffffffu, s, d);
        const float mn = (s > m || s != s) ? s : m;
        const float sc = (m == mn) ? 1.f : ex2((m - mn) * c);
        const float p = (s == -INFINITY) ? 0.f : ex2((s - mn) * c);
        m = mn;
        l = l * sc + p;
        a0 = a0 * sc + p * bf_lo(vv.x); a1 = a1 * sc + p * bf_hi(vv.x);
        a2 = a2 * sc + p * bf_lo(vv.y); a3 = a3 * sc + p * bf_hi(vv.y);
    }
    const float inv = 1.f / l;
    *(uint2*)(out + lane * 8) = make_uint2(pack_bf16(a0 * inv, a1 * inv), pack_bf16(a2 * inv, a3 * inv));
}

__global__ void __cluster_dims__(2, 1, 1) __launch_bounds__(kThreads, 1)
gqa_attn_kernel(const __grid_constant__ CUtensorMap mapQ, const __grid_constant__ CUtensorMap mapK,
                const __grid_constant__ CUtensorMap mapV, const __grid_constant__ CUtensorMap mapO,
                const uint8_t* __restrict__ gQ, const uint8_t* __restrict__ gK, const uint8_t* __restrict__ gV, uint8_t* __restrict__ gO) {
    if (threadIdx.x == 0) {
        const uint8_t* q = gQ + (size_t)blockIdx.x * (3 * kQBytes);
        const size_t kv = (size_t)(blockIdx.x >> 1) * (kSk * kD * 2) + (blockIdx.x & 1) * (kTileBytes / 2);
        if (DESC_FIRST) {
            asm volatile("prefetch.tensormap [%0];" :: "l"(&mapQ) : "memory");
            asm volatile("prefetch.tensormap [%0];" :: "l"(&mapK) : "memory");
            asm volatile("prefetch.tensormap [%0];" :: "l"(&mapV) : "memory");
            asm volatile("prefetch.tensormap [%0];" :: "l"(&mapO) : "memory");
        }
        if (NPF > 0) l2_prefetch(q);
        if (NPF > 1) l2_prefetch(gK + kv);
        if (NPF > 2) l2_prefetch(q + 2 * kQBytes);
        if (NPF > 3) l2_prefetch(gV + kv);
        if (NPF > 4) l2_prefetch(q + kQBytes);
        if (NPF > 5) l2_prefetch(gK + kv + kTileBytes);
        if (NPF > 6) l2_prefetch(gV + kv + kTileBytes);
        if (NPF > 7) l2_prefetch(gK + kv + 2 * kTileBytes);
        if (!DESC_FIRST) {
            asm volatile("prefetch.tensormap [%0];" :: "l"(&mapQ) : "memory");
            asm volatile("prefetch.tensormap [%0];" :: "l"(&mapK) : "memory");
            asm volatile("prefetch.tensormap [%0];" :: "l"(&mapV) : "memory");
            asm volatile("prefetch.tensormap [%0];" :: "l"(&mapO) : "memory");
        }
    }
    uint32_t tstart;
    asm volatile("mov.u32 %0, %%globaltimer_lo;" : "=r"(tstart) :: "memory");
    extern __shared__ uint8_t smem_raw[];
    const uint32_t smem = (smem_u32(smem_raw) + 1023) & ~1023u;
    const uint32_t barQ = smem + kSmemBar;
    const uint32_t barFull = barQ + 3 * 8;
    const uint32_t barEmpty = barFull + kNumTiles * 8;
    const uint32_t barDone = barEmpty + (kNumTiles - kStages) * 8;
    const int wg = __shfl_sync(0xffffffffu, threadIdx.x >> 7, 0);
    const int head = blockIdx.x >> 1;
    const uint32_t rank = blockIdx.x & 1;
    const int qgroup0 = (head * kRowsPerHead + rank * 192) >> 3;

    PROFL(0);
    PROFG(71);
    if (threadIdx.x == 0) {
#pragma unroll
        for (int i = 0; i < 31; i++) mbar_init(barQ + 8 * i, i < 3 + kNumTiles ? 1 : (i < 30 ? 24 : 12));
        asm volatile("fence.mbarrier_init.release.cluster;" ::: "memory");
        asm volatile("fence.proxy.async.shared::cta;" ::: "memory");
        mbar_expect_tx(barQ, kQBytes);
        tma_load(smem + kSmemQ, &mapQ, qgroup0, barQ);
    }
    __syncwarp();
    asm volatile("barrier.cluster.arrive.relaxed.aligned;" ::: "memory");
    asm volatile("barrier.cluster.wait.aligned;" ::: "memory");

    if (wg == 0) {
        asm volatile("setmaxnreg.dec.sync.aligned.u32 32;");
        if (threadIdx.x == 0) {
            const int kvgroup0 = head * (kSk / 8) + rank * 8;
            auto pace = [&](int unit) {
                if (PACE > 0) {
                    const uint32_t due = (uint32_t)(unit * PACE - LEAD);
                    uint32_t now;
                    do { asm volatile("mov.u32 %0, %%globaltimer_lo;" : "=r"(now)); } while (now - tstart < due);
                }
            };
#pragma unroll 1
            for (int t = 0; t < kNumTiles; t++) {
                const int s = t % kStages;
                if (t >= kStages) mbar_wait_bounded(barEmpty + 8 * (t - kStages));
                else if (t > 0) pace(t == 1 ? 3 : t + 3);
                mbar_expect_tx(barFull + 8 * t, kTileBytes);
                tma_load_mc(smem + kSmemKV + s * kTileBytes + rank * (kTileBytes / 2), (t & 1) ? &mapV : &mapK,
                            kvgroup0 + (t >> 1) * (kBN / 8), barFull + 8 * t, (uint16_t)3);
                if (t == 0) { pace(2); mbar_expect_tx(barQ + 16, kQBytes); tma_load(smem + kSmemQ + 2 * kQBytes, &mapQ, qgroup0 + 16, barQ + 16); }
                if (t == 1) { pace(4); mbar_expect_tx(barQ + 8, kQBytes); tma_load(smem + kSmemQ + kQBytes, &mapQ, qgroup0 + 8, barQ + 8); }
                PROF(1 + t);
            }
            mbar_wait_bounded(barDone);
            PROF_DUMP();
        }
    } else {
        asm volatile("setmaxnreg.inc.sync.aligned.u32 160;");
        const int w = wg - 1;
        const int lane = threadIdx.x & 31;
        const int warp = (threadIdx.x >> 5) & 3;
        const uint32_t sQ = smem + kSmemQ + w * kQBytes;
        const uint64_t descQ = make_desc(sQ, 16, 2048);
        const float c = 0.08838834764831845f * 1.4426950408889634f;
        const int my_bar = threadIdx.x >> 7;
        const int next_bar = my_bar == 3 ? 1 : my_bar + 1;
        const uint32_t relAddr = map_to_cta(barEmpty, lane & 1);

        float o[64];
        float s[64];
        uint32_t p[32];
        float m0, m1, l0, l1;
        uint32_t stage = smem + kSmemKV;

        auto issue_qk = [&]() {
            const uint64_t descK = make_desc(stage, 16, 2048);
            wgmma_fence();
#pragma unroll
            for (int k = 0; k < 8; k++) {
                const uint32_t off = ((k >> 2) * 1024 + (k & 3) * 32) >> 4;
                if (k == 0) wgmma_ss_init(s, descQ + off, descK + off);
                else wgmma_ss(s, descQ + off, descK + off);
            }
            wgmma_commit();
        };
        auto release = [&](int t) {
            if (t + kStages < kNumTiles) { if (lane < 2) mbar_arrive_cluster(relAddr + 8 * t); }
            stage += kTileBytes;
            if (stage == smem + kSmemKV + kStages * kTileBytes) stage = smem + kSmemKV;
        };
        auto row_max = [&](float& mx0, float& mx1) {
            mx0 = fmaxf(s[0], s[1]); mx1 = fmaxf(s[2], s[3]);
            float mx2 = fmaxf(s[4], s[5]), mx3 = fmaxf(s[6], s[7]);
#pragma unroll
            for (int i = 2; i < 16; i += 2) {
                mx0 = fmaxf(mx0, fmaxf(s[4 * i + 0], s[4 * i + 1]));
                mx1 = fmaxf(mx1, fmaxf(s[4 * i + 2], s[4 * i + 3]));
                mx2 = fmaxf(mx2, fmaxf(s[4 * i + 4], s[4 * i + 5]));
                mx3 = fmaxf(mx3, fmaxf(s[4 * i + 6], s[4 * i + 7]));
            }
            mx0 = fmaxf(mx0, mx2); mx1 = fmaxf(mx1, mx3);
            mx0 = fmaxf(mx0, __shfl_xor_sync(0xffffffffu, mx0, 1));
            mx1 = fmaxf(mx1, __shfl_xor_sync(0xffffffffu, mx1, 1));
            mx0 = fmaxf(mx0, __shfl_xor_sync(0xffffffffu, mx0, 2));
            mx1 = fmaxf(mx1, __shfl_xor_sync(0xffffffffu, mx1, 2));
        };
        float mc0, mc1, l2, l3;
        float x[64];
        auto scale_sub = [&]() {
#pragma unroll
            for (int i = 0; i < 16; i++) {
                x[4 * i + 0] = fmaf(s[4 * i + 0], c, mc0);
                x[4 * i + 1] = fmaf(s[4 * i + 1], c, mc0);
                x[4 * i + 2] = fmaf(s[4 * i + 2], c, mc1);
                x[4 * i + 3] = fmaf(s[4 * i + 3], c, mc1);
            }
        };
        auto exp_pack = [&](int k0, int k1) {
#pragma unroll
            for (int i = 2 * k0; i < 2 * k1; i++) {
                const float e0 = ex2(x[4 * i + 0]);
                const float e1 = ex2(x[4 * i + 1]);
                const float e2 = ex2(x[4 * i + 2]);
                const float e3 = ex2(x[4 * i + 3]);
                l0 += e0; l2 += e1; l1 += e2; l3 += e3;
                p[2 * i + 0] = pack_bf16(e0, e1);
                p[2 * i + 1] = pack_bf16(e2, e3);
            }
        };

        mbar_wait(barQ + 8 * w);
        PROF(1);
        mbar_wait(barFull);
        if (ORDER && w != 0) named_sync(my_bar);
        issue_qk();
        if (ORDER) named_arrive(w == 0 ? 3 : next_bar);
        PROF(2);
        wgmma_wait0();
        fence_regs(s);
        PROFL(3);
        release(0);
        row_max(m0, m1);
        mc0 = -m0 * c; mc1 = -m1 * c;
        l0 = l1 = l2 = l3 = 0.f;
        scale_sub();
        exp_pack(0, SPLIT);
#pragma unroll
        for (int i = 0; i < 64; i++) o[i] = 0.f;

#pragma unroll 1
        for (int j = 0;; j++) {
            PROF(4 + j * 6 + 0);
            mbar_wait(barFull + 16 * j + 8);
            if (ORDER) named_sync(my_bar);
            {
                const uint64_t descV = make_desc(stage, 1024, 2048);
                exp_pack(SPLIT, 8);
                wgmma_fence();
#pragma unroll
                for (int k = 0; k < 8; k++)
                    wgmma_rs(o, p[4 * k + 0], p[4 * k + 1], p[4 * k + 2], p[4 * k + 3], descV + ((k * 4096) >> 4));
                wgmma_commit();
            }
            if (j == kNumBlocks - 1) {
                if (ORDER && w != 1) named_arrive(2);
                PROF(4 + j * 6 + 1);
                break;
            }
            if (ORDER) named_arrive(next_bar);
            PROF(4 + j * 6 + 1);
            wgmma_wait0();
            fence_regs(o);
            PROFL(4 + j * 6 + 2);
            release(2 * j + 1);

            mbar_wait(barFull + 16 * j + 16);
            if (ORDER) named_sync(my_bar);
            issue_qk();
            if (ORDER) named_arrive(next_bar);
            PROF(4 + j * 6 + 3);
            wgmma_wait0();
            fence_regs(s);
            PROF(4 + j * 6 + 4);
            release(2 * j + 2);
            scale_sub();
            exp_pack(0, SPLIT);
        }
        l0 += l2; l1 += l3;

        l0 += __shfl_xor_sync(0xffffffffu, l0, 1);
        l1 += __shfl_xor_sync(0xffffffffu, l1, 1);
        l0 += __shfl_xor_sync(0xffffffffu, l0, 2);
        l1 += __shfl_xor_sync(0xffffffffu, l1, 2);
        float i0, i1;
        asm("rcp.approx.ftz.f32 %0, %1;" : "=f"(i0) : "f"(l0));
        asm("rcp.approx.ftz.f32 %0, %1;" : "=f"(i1) : "f"(l1));
        const bool suspicious = __any_sync(0xffffffffu, !(l0 <= 4096.f) || !(l1 <= 4096.f));
        if (lane == 0 && i0 != -1.f && i1 != -1.f) asm volatile("mbarrier.arrive.shared::cta.b64 _, [%0];" :: "r"(barDone) : "memory");
        wgmma_wait0();
        fence_regs(o);
        PROFL(48);
        const uint32_t sO = sQ + warp * 4096;
        uint8_t* gOw = gO + ((size_t)blockIdx.x * 192 + w * 64 + warp * 16) * 256;
        const int r = lane & 7, g = (lane >> 3) & 1, chi = lane >> 4;
#pragma unroll
        for (int n = 0; n < 8; n++) {
            const int ch = 2 * n + chi;
            const uint32_t addr = sO + g * 2048 + (n >> 2) * 1024 + r * 128 + (((ch & 7) ^ r) << 4);
            const uint32_t x0 = pack_bf16(o[8 * n + 0] * i0, o[8 * n + 1] * i0);
            const uint32_t x1 = pack_bf16(o[8 * n + 2] * i1, o[8 * n + 3] * i1);
            const uint32_t x2 = pack_bf16(o[8 * n + 4] * i0, o[8 * n + 5] * i0);
            const uint32_t x3 = pack_bf16(o[8 * n + 6] * i1, o[8 * n + 7] * i1);
            asm volatile("stmatrix.sync.aligned.m8n8.x4.shared.b16 [%0], {%1, %2, %3, %4};"
                         :: "r"(addr), "r"(x0), "r"(x1), "r"(x2), "r"(x3) : "memory");
        }
        PROF(66);
        asm volatile("fence.proxy.async.shared::cta;" ::: "memory");
        __syncwarp();
        PROF(67);
        if (lane == 0) {
            tma_store(&mapO, qgroup0 + w * 8 + warp * 2, sO);
            asm volatile("cp.async.bulk.commit_group;" ::: "memory");
            PROF(68);
            asm volatile("cp.async.bulk.wait_group.read 0;" ::: "memory");
        }
        if (suspicious) {
            float t0 = 0.f, t1 = 0.f;
#pragma unroll
            for (int i = 0; i < 16; i++) {
                t0 = fmaf(o[4 * i + 0], 0.f, fmaf(o[4 * i + 1], 0.f, t0));
                t1 = fmaf(o[4 * i + 2], 0.f, fmaf(o[4 * i + 3], 0.f, t1));
            }
            const uint32_t bad0 = __ballot_sync(0xffffffffu, !(l0 < 0x1p100f) || t0 != 0.f);
            const uint32_t bad1 = __ballot_sync(0xffffffffu, !(l1 < 0x1p100f) || t1 != 0.f);
            if (lane == 0) asm volatile("cp.async.bulk.wait_group 0;" ::: "memory");
            __syncwarp();
#pragma unroll 1
            for (int r = 0; r < 16; r++) {
                if ((((r < 8 ? bad0 : bad1) >> (4 * (r & 7))) & 0xF) == 0) continue;
                const size_t row = (size_t)blockIdx.x * 192 + w * 64 + warp * 16 + r;
                exact_row(gQ + row * 256, gK + (size_t)head * (kSk * 256), gV + (size_t)head * (kSk * 256), gO + row * 256, lane);
            }
        }
        PROFL(70);
        PROFG(72);
        PROF_DUMP();
    }
}

typedef CUresult (*EncodeFn)(CUtensorMap*, CUtensorMapDataType, cuuint32_t, void*, const cuuint64_t*, const cuuint64_t*,
                             const cuuint32_t*, const cuuint32_t*, CUtensorMapInterleave, CUtensorMapSwizzle,
                             CUtensorMapL2promotion, CUtensorMapFloatOOBfill);

void make_map(EncodeFn enc, CUtensorMap* map, const void* ptr, uint64_t rows, uint32_t box_groups) {
    cuuint64_t dims[4] = {64, 8, 2, rows / 8};
    cuuint64_t strides[3] = {256, 128, 2048};
    cuuint32_t box[4] = {64, 8, 2, box_groups};
    cuuint32_t estr[4] = {1, 1, 1, 1};
    enc(map, CU_TENSOR_MAP_DATA_TYPE_BFLOAT16, 4, const_cast<void*>(ptr), dims, strides, box, estr,
        CU_TENSOR_MAP_INTERLEAVE_NONE, CU_TENSOR_MAP_SWIZZLE_128B, CU_TENSOR_MAP_L2_PROMOTION_L2_256B,
        CU_TENSOR_MAP_FLOAT_OOB_FILL_NONE);
}

}

extern "C" void kernel_launch(void* const* d_in, const int* in_sizes, int n_in, void* d_out, int out_size) {
    static EncodeFn enc = nullptr;
    if (!enc) {
        void* fn = nullptr;
        cudaDriverEntryPointQueryResult st;
        cudaGetDriverEntryPoint("cuTensorMapEncodeTiled", &fn, cudaEnableDefault, &st);
        enc = (EncodeFn)fn;
        cudaFuncSetAttribute(gqa_attn_kernel, cudaFuncAttributeMaxDynamicSharedMemorySize, kSmemTotal);
    }
    CUtensorMap mq, mk, mv, mo;
    make_map(enc, &mq, d_in[0], (uint64_t)kNumKVHeads * kRowsPerHead, 8);
    make_map(enc, &mk, d_in[1], (uint64_t)kNumKVHeads * kSk, 8);
    make_map(enc, &mv, d_in[2], (uint64_t)kNumKVHeads * kSk, 8);
    make_map(enc, &mo, d_out, (uint64_t)kNumKVHeads * kRowsPerHead, 2);
    gqa_attn_kernel<<<2 * kNumKVHeads, kThreads, kSmemTotal>>>(mq, mk, mv, mo, (const uint8_t*)d_in[0], (const uint8_t*)d_in[1], (const uint8_t*)d_in[2], (uint8_t*)d_out);
}
```

```cpp
#include <cuda_runtime.h>
#include <cuda_bf16.h>
#include <cuda.h>
#include <stdint.h>

namespace {

constexpr int kD = 128;
constexpr int kSk = 1024;
constexpr int kRowsPerHead = 384;
constexpr int kRowsPerCta = 192;
constexpr int kNumKVHeads = 64;
constexpr int kBN = 128;
constexpr int kNumBlocks = kSk / kBN;
constexpr int kNumTiles = 2 * kNumBlocks;
constexpr int kStages = 5;
constexpr int kTileBytes = kBN * kD * 2;
constexpr int kQBytes = 64 * kD * 2;
constexpr int kSmemQ = 0;
constexpr int kSmemKV = 3 * kQBytes;
constexpr int kSmemBar = kSmemKV + kStages * kTileBytes;
constexpr int kSmemStash = kSmemBar + 256;
constexpr int kSmemTotal = kSmemStash + 384 * 16 + 1024;
constexpr int kThreads = 512;
constexpr int kSplit = 6;
constexpr float kScaleLog2e = 0.08838834764831845f * 1.4426950408889634f;

constexpr int kPace = 680;
constexpr int kLead = 480;
constexpr int kSlow = 80;
constexpr int kStagger = 340;
constexpr int kNumPacedTiles = 8;
__device__ __forceinline__ int due_time(int u) { return u * kPace - kLead + (u > 5 ? (u - 5) * kSlow : 0); }

__device__ __forceinline__ uint32_t smem_u32(const void* p) { return (uint32_t)__cvta_generic_to_shared(p); }
__device__ __forceinline__ uint32_t timer_ns() {
    uint32_t t; asm volatile("mov.u32 %0, %%globaltimer_lo;" : "=r"(t) :: "memory"); return t;
}

__device__ __forceinline__ void mbar_init(uint32_t bar, uint32_t count) {
    asm volatile("mbarrier.init.shared::cta.b64 [%0], %1;" :: "r"(bar), "r"(count) : "memory");
}
__device__ __forceinline__ void mbar_expect_tx(uint32_t bar, uint32_t bytes) {
    asm volatile("mbarrier.arrive.expect_tx.shared::cta.b64 _, [%0], %1;" :: "r"(bar), "r"(bytes) : "memory");
}
__device__ __forceinline__ void mbar_wait(uint32_t bar) {
    uint32_t ok;
    do {
        asm volatile("{\n\t.reg .pred p;\n\t"
                     "mbarrier.try_wait.parity.shared::cta.b64 p, [%1], 0;\n\t"
                     "selp.u32 %0, 1, 0, p;\n\t}"
                     : "=r"(ok) : "r"(bar) : "memory");
    } while (!ok);
}
__device__ __forceinline__ void mbar_wait_bounded(uint32_t bar, uint32_t tstart) {
    for (;;) {
        uint32_t ok;
        asm volatile("{\n\t.reg .pred p;\n\t"
                     "mbarrier.try_wait.parity.shared::cta.b64 p, [%1], 0, %2;\n\t"
                     "selp.u32 %0, 1, 0, p;\n\t}"
                     : "=r"(ok) : "r"(bar), "r"(1000000u) : "memory");
        if (ok) return;
        if (timer_ns() - tstart > 2000000000u) __trap();
    }
}
__device__ __forceinline__ uint32_t map_to_cta(uint32_t addr, uint32_t cta) {
    uint32_t r; asm("mapa.shared::cluster.u32 %0, %1, %2;" : "=r"(r) : "r"(addr), "r"(cta)); return r;
}
__device__ __forceinline__ void mbar_arrive_cluster(uint32_t cluster_addr) {
    asm volatile("mbarrier.arrive.shared::cluster.b64 _, [%0];" :: "r"(cluster_addr) : "memory");
}
__device__ __forceinline__ void tma_load(uint32_t dst, const CUtensorMap* map, int group, uint32_t bar) {
    asm volatile("cp.async.bulk.tensor.4d.shared::cluster.global.mbarrier::complete_tx::bytes "
                 "[%0], [%1, {%4, %4, %4, %2}], [%3];"
                 :: "r"(dst), "l"(map), "r"(group), "r"(bar), "r"(0) : "memory");
}
__device__ __forceinline__ void tma_load_mc(uint32_t dst, const CUtensorMap* map, int group, uint32_t bar, uint16_t mask) {
    asm volatile("cp.async.bulk.tensor.4d.shared::cluster.global.mbarrier::complete_tx::bytes.multicast::cluster "
                 "[%0], [%1, {%5, %5, %5, %2}], [%3], %4;"
                 :: "r"(dst), "l"(map), "r"(group), "r"(bar), "h"(mask), "r"(0) : "memory");
}
__device__ __forceinline__ void l2_prefetch_16k(const void* p) {
    asm volatile("cp.async.bulk.prefetch.L2.global [%0], 16384;" :: "l"(p) : "memory");
}
__device__ __forceinline__ void turn_wait(int id) { asm volatile("bar.sync %0, 256;" :: "r"(id) : "memory"); }
__device__ __forceinline__ void turn_pass(int id) { asm volatile("bar.arrive %0, 256;" :: "r"(id) : "memory"); }

__device__ __forceinline__ void wgmma_fence() { asm volatile("wgmma.fence.sync.aligned;" ::: "memory"); }
__device__ __forceinline__ void wgmma_commit() { asm volatile("wgmma.commit_group.sync.aligned;" ::: "memory"); }
__device__ __forceinline__ void wgmma_wait0() { asm volatile("wgmma.wait_group.sync.aligned 0;" ::: "memory"); }
__device__ __forceinline__ uint64_t make_desc(uint32_t addr, uint32_t lbo, uint32_t sbo) {
    return (uint64_t)((addr & 0x3FFFF) >> 4) | ((uint64_t)(lbo >> 4) << 16) | ((uint64_t)(sbo >> 4) << 32) | (1ull << 62);
}

#define ACC64(d) \
    "+f"(d[0]), "+f"(d[1]), "+f"(d[2]), "+f"(d[3]), "+f"(d[4]), "+f"(d[5]), "+f"(d[6]), "+f"(d[7]), \
    "+f"(d[8]), "+f"(d[9]), "+f"(d[10]), "+f"(d[11]), "+f"(d[12]), "+f"(d[13]), "+f"(d[14]), "+f"(d[15]), \
    "+f"(d[16]), "+f"(d[17]), "+f"(d[18]), "+f"(d[19]), "+f"(d[20]), "+f"(d[21]), "+f"(d[22]), "+f"(d[23]), \
    "+f"(d[24]), "+f"(d[25]), "+f"(d[26]), "+f"(d[27]), "+f"(d[28]), "+f"(d[29]), "+f"(d[30]), "+f"(d[31]), \
    "+f"(d[32]), "+f"(d[33]), "+f"(d[34]), "+f"(d[35]), "+f"(d[36]), "+f"(d[37]), "+f"(d[38]), "+f"(d[39]), \
    "+f"(d[40]), "+f"(d[41]), "+f"(d[42]), "+f"(d[43]), "+f"(d[44]), "+f"(d[45]), "+f"(d[46]), "+f"(d[47]), \
    "+f"(d[48]), "+f"(d[49]), "+f"(d[50]), "+f"(d[51]), "+f"(d[52]), "+f"(d[53]), "+f"(d[54]), "+f"(d[55]), \
    "+f"(d[56]), "+f"(d[57]), "+f"(d[58]), "+f"(d[59]), "+f"(d[60]), "+f"(d[61]), "+f"(d[62]), "+f"(d[63])
#define OUT64(d) \
    "=f"(d[0]), "=f"(d[1]), "=f"(d[2]), "=f"(d[3]), "=f"(d[4]), "=f"(d[5]), "=f"(d[6]), "=f"(d[7]), \
    "=f"(d[8]), "=f"(d[9]), "=f"(d[10]), "=f"(d[11]), "=f"(d[12]), "=f"(d[13]), "=f"(d[14]), "=f"(d[15]), \
    "=f"(d[16]), "=f"(d[17]), "=f"(d[18]), "=f"(d[19]), "=f"(d[20]), "=f"(d[21]), "=f"(d[22]), "=f"(d[23]), \
    "=f"(d[24]), "=f"(d[25]), "=f"(d[26]), "=f"(d[27]), "=f"(d[28]), "=f"(d[29]), "=f"(d[30]), "=f"(d[31]), \
    "=f"(d[32]), "=f"(d[33]), "=f"(d[34]), "=f"(d[35]), "=f"(d[36]), "=f"(d[37]), "=f"(d[38]), "=f"(d[39]), \
    "=f"(d[40]), "=f"(d[41]), "=f"(d[42]), "=f"(d[43]), "=f"(d[44]), "=f"(d[45]), "=f"(d[46]), "=f"(d[47]), \
    "=f"(d[48]), "=f"(d[49]), "=f"(d[50]), "=f"(d[51]), "=f"(d[52]), "=f"(d[53]), "=f"(d[54]), "=f"(d[55]), \
    "=f"(d[56]), "=f"(d[57]), "=f"(d[58]), "=f"(d[59]), "=f"(d[60]), "=f"(d[61]), "=f"(d[62]), "=f"(d[63])
#define REGS64 \
    "{%0, %1, %2, %3, %4, %5, %6, %7, %8, %9, %10, %11, %12, %13, %14, %15, " \
    "%16, %17, %18, %19, %20, %21, %22, %23, %24, %25, %26, %27, %28, %29, %30, %31, " \
    "%32, %33, %34, %35, %36, %37, %38, %39, %40, %41, %42, %43, %44, %45, %46, %47, " \
    "%48, %49, %50, %51, %52, %53, %54, %55, %56, %57, %58, %59, %60, %61, %62, %63}"

__device__ __forceinline__ void wgmma_ss(float (&d)[64], uint64_t da, uint64_t db) {
    asm volatile("wgmma.mma_async.sync.aligned.m64n128k16.f32.bf16.bf16 " REGS64 ", %64, %65, 1, 1, 1, 0, 0;"
                 : ACC64(d) : "l"(da), "l"(db));
}
__device__ __forceinline__ void wgmma_ss_init(float (&d)[64], uint64_t da, uint64_t db) {
    asm volatile("wgmma.mma_async.sync.aligned.m64n128k16.f32.bf16.bf16 " REGS64 ", %64, %65, 0, 1, 1, 0, 0;"
                 : OUT64(d) : "l"(da), "l"(db));
}
__device__ __forceinline__ void wgmma_rs(float (&d)[64], uint32_t a0, uint32_t a1, uint32_t a2, uint32_t a3, uint64_t db) {
    asm volatile("wgmma.mma_async.sync.aligned.m64n128k16.f32.bf16.bf16 " REGS64 ", {%64, %65, %66, %67}, %68, 1, 1, 1, 1;"
                 : ACC64(d) : "r"(a0), "r"(a1), "r"(a2), "r"(a3), "l"(db));
}
__device__ __forceinline__ void fence_regs(float (&d)[64]) {
#pragma unroll
    for (int i = 0; i < 64; i++) asm volatile("" : "+f"(d[i]) :: "memory");
}

__device__ __forceinline__ float ex2(float x) { float y; asm("ex2.approx.ftz.f32 %0, %1;" : "=f"(y) : "f"(x)); return y; }
__device__ __forceinline__ uint32_t pack_bf16(float lo, float hi) {
    uint32_t r; asm("cvt.rn.bf16x2.f32 %0, %1, %2;" : "=r"(r) : "f"(hi), "f"(lo)); return r;
}
__device__ __forceinline__ float bf_lo(uint32_t v) { return __uint_as_float(v << 16); }
__device__ __forceinline__ float bf_hi(uint32_t v) { return __uint_as_float(v & 0xffff0000u); }

__device__ __forceinline__ void exact_row(const uint8_t* q, const uint8_t* k, const uint8_t* v, uint8_t* out, int lane) {
    const uint2 qq = *(const uint2*)(q + lane * 8);
    const float q0 = bf_lo(qq.x), q1 = bf_hi(qq.x), q2 = bf_lo(qq.y), q3 = bf_hi(qq.y);
    float m = -INFINITY, l = 0.f, a0 = 0.f, a1 = 0.f, a2 = 0.f, a3 = 0.f;
#pragma unroll 4
    for (int j = 0; j < kSk; j++) {
        const uint2 kk = *(const uint2*)(k + j * 256 + lane * 8);
        const uint2 vv = *(const uint2*)(v + j * 256 + lane * 8);
        float s = q0 * bf_lo(kk.x) + q1 * bf_hi(kk.x) + q2 * bf_lo(kk.y) + q3 * bf_hi(kk.y);
#pragma unroll
        for (int d = 16; d > 0; d >>= 1) s += __shfl_xor_sync(0xffffffffu, s, d);
        const float mn = (s > m || s != s) ? s : m;
        const float sc = (m == mn) ? 1.f : ex2((m - mn) * kScaleLog2e);
        const float p = (s == -INFINITY) ? 0.f : ex2((s - mn) * kScaleLog2e);
        m = mn;
        l = l * sc + p;
        a0 = a0 * sc + p * bf_lo(vv.x); a1 = a1 * sc + p * bf_hi(vv.x);
        a2 = a2 * sc + p * bf_lo(vv.y); a3 = a3 * sc + p * bf_hi(vv.y);
    }
    const float inv = 1.f / l;
    *(uint2*)(out + lane * 8) = make_uint2(pack_bf16(a0 * inv, a1 * inv), pack_bf16(a2 * inv, a3 * inv));
}

__global__ void __cluster_dims__(2, 1, 1) __launch_bounds__(kThreads, 1)
gqa_attn_kernel(const uint8_t* __restrict__ gQ, const uint8_t* __restrict__ gK, const uint8_t* __restrict__ gV,
                uint8_t* __restrict__ gO, const __grid_constant__ CUtensorMap mapQ,
                const __grid_constant__ CUtensorMap mapK, const __grid_constant__ CUtensorMap mapV) {
    if (threadIdx.x == 32) l2_prefetch_16k(gQ + (size_t)blockIdx.x * (3 * kQBytes));
    if (threadIdx.x == 0) {
        asm volatile("prefetch.tensormap [%0];" :: "l"(&mapQ) : "memory");
        asm volatile("prefetch.tensormap [%0];" :: "l"(&mapK) : "memory");
        asm volatile("prefetch.tensormap [%0];" :: "l"(&mapV) : "memory");
    }
    const int head = blockIdx.x >> 1;
    const uint32_t rank = blockIdx.x & 1;
    const uint32_t tstart = __shfl_sync(0xffffffffu, timer_ns() + (threadIdx.x & 31), 0);
    auto pace = [&](int unit) {
        const int due = due_time(unit) + head * kStagger / kNumKVHeads;
        for (;;) {
            const int left = due - (int)(timer_ns() - tstart);
            if (left <= 0) break;
            if (left > 64) __nanosleep(left >> 1);
        }
    };

    extern __shared__ uint8_t smem_raw[];
    const uint32_t smem = (smem_u32(smem_raw) + 1023) & ~1023u;
    const uint32_t barQ = smem + kSmemBar;
    const uint32_t barFull = barQ + 3 * 8;
    const uint32_t barEmpty = barFull + kNumTiles * 8;
    const uint32_t barDone = barEmpty + (kNumTiles - kStages) * 8;
    const int wg = __shfl_sync(0xffffffffu, threadIdx.x >> 7, 0);
    const int qgroup0 = (head * kRowsPerHead + rank * kRowsPerCta) >> 3;

    if (threadIdx.x == 0) {
#pragma unroll
        for (int i = 0; i < 3 + kNumTiles; i++) mbar_init(barQ + 8 * i, 1);
#pragma unroll
        for (int i = 0; i < kNumTiles - kStages; i++) mbar_init(barEmpty + 8 * i, 24);
        mbar_init(barDone, 12);
        asm volatile("fence.mbarrier_init.release.cluster;" ::: "memory");
        asm volatile("fence.proxy.async.shared::cta;" ::: "memory");
        mbar_expect_tx(barQ, kQBytes);
        tma_load(smem + kSmemQ, &mapQ, qgroup0, barQ);
    }
    __syncwarp();
    asm volatile("barrier.cluster.arrive.relaxed.aligned;" ::: "memory");
    if (threadIdx.x == 256) {
        pace(1);
        l2_prefetch_16k(gK + (size_t)head * (kSk * kD * 2) + rank * (kTileBytes / 2));
    }
    __syncwarp();
    asm volatile("barrier.cluster.wait.aligned;" ::: "memory");

    if (wg == 0) {
        asm volatile("setmaxnreg.dec.sync.aligned.u32 32;");
        if (threadIdx.x == 0) {
            const int kvgroup0 = head * (kSk / 8) + rank * 8;
#pragma unroll 1
            for (int t = 0; t < kNumTiles; t++) {
                if (t >= kStages) mbar_wait_bounded(barEmpty + 8 * (t - kStages), tstart);
                if (t < kNumPacedTiles) pace(t == 0 ? 1 : t + 3);
                mbar_expect_tx(barFull + 8 * t, kTileBytes);
                tma_load_mc(smem + kSmemKV + (t % kStages) * kTileBytes + rank * (kTileBytes / 2), (t & 1) ? &mapV : &mapK,
                            kvgroup0 + (t >> 1) * (kBN / 8), barFull + 8 * t, (uint16_t)3);
                if (t == 0) {
                    pace(2);
                    mbar_expect_tx(barQ + 16, kQBytes);
                    tma_load(smem + kSmemQ + 2 * kQBytes, &mapQ, qgroup0 + 16, barQ + 16);
                    pace(3);
                    mbar_expect_tx(barQ + 8, kQBytes);
                    tma_load(smem + kSmemQ + kQBytes, &mapQ, qgroup0 + 8, barQ + 8);
                }
            }
            mbar_wait_bounded(barDone, tstart);
        }
    } else {
        asm volatile("setmaxnreg.inc.sync.aligned.u32 160;");
        const int w = wg - 1;
        const int lane = threadIdx.x & 31;
        const int warp = (threadIdx.x >> 5) & 3;
        const uint32_t sQ = smem + kSmemQ + w * kQBytes;
        const uint64_t descQ = make_desc(sQ, 16, 2048);
        const int my_turn = threadIdx.x >> 7;
        const int next_turn = my_turn == 3 ? 1 : my_turn + 1;
        const uint32_t relAddr = map_to_cta(barEmpty, lane & 1);

        const uint32_t stash = smem + kSmemStash + (threadIdx.x - 128) * 16;
        {
            const uint32_t sO = sQ + warp * 4096;
            const uint32_t stA = sO + ((lane >> 3) & 1) * 1024 + (lane & 7) * 128 + (((lane >> 4) ^ (lane & 7)) << 4);
            const uint32_t ldA = sO + (lane >> 3) * 128 + (((lane & 7) ^ (lane >> 3)) << 4);
            const uint64_t g = (uint64_t)gO + ((size_t)blockIdx.x * kRowsPerCta + w * 64 + warp * 16 + (lane >> 3)) * 256 + (lane & 7) * 16;
            asm volatile("st.shared.v4.u32 [%0], {%1, %2, %3, %4};"
                         :: "r"(stash), "r"(stA), "r"(ldA), "r"((uint32_t)g), "r"((uint32_t)(g >> 32)) : "memory");
        }

        float o[64], s[64], x[64];
        uint32_t p[32];
        float mc0, mc1;
        float l0 = 0.f, l1 = 0.f, l2 = 0.f, l3 = 0.f;
        uint32_t stage = smem + kSmemKV;

        auto issue_qk = [&]() {
            const uint64_t descK = make_desc(stage, 16, 2048);
            wgmma_fence();
#pragma unroll
            for (int k = 0; k < 8; k++) {
                const uint32_t off = ((k >> 2) * 1024 + (k & 3) * 32) >> 4;
                if (k == 0) wgmma_ss_init(s, descQ + off, descK + off);
                else wgmma_ss(s, descQ + off, descK + off);
            }
            wgmma_commit();
        };
        auto release = [&](int t) {
            if (t + kStages < kNumTiles) { if (lane < 2) mbar_arrive_cluster(relAddr + 8 * t); }
            stage += kTileBytes;
            if (stage == smem + kSmemKV + kStages * kTileBytes) stage = smem + kSmemKV;
        };
        auto scale_sub = [&]() {
#pragma unroll
            for (int i = 0; i < 16; i++) {
                x[4 * i + 0] = fmaf(s[4 * i + 0], kScaleLog2e, mc0);
                x[4 * i + 1] = fmaf(s[4 * i + 1], kScaleLog2e, mc0);
                x[4 * i + 2] = fmaf(s[4 * i + 2], kScaleLog2e, mc1);
                x[4 * i + 3] = fmaf(s[4 * i + 3], kScaleLog2e, mc1);
            }
        };
        auto exp_pack = [&](int k0, int k1) {
#pragma unroll
            for (int i = 2 * k0; i < 2 * k1; i++) {
                const float e0 = ex2(x[4 * i + 0]);
                const float e1 = ex2(x[4 * i + 1]);
                const float e2 = ex2(x[4 * i + 2]);
                const float e3 = ex2(x[4 * i + 3]);
                l0 += e0; l2 += e1; l1 += e2; l3 += e3;
                p[2 * i + 0] = pack_bf16(e0, e1);
                p[2 * i + 1] = pack_bf16(e2, e3);
            }
        };

        mbar_wait(barQ + 8 * w);
        mbar_wait(barFull);
        if (w != 0) turn_wait(my_turn);
        issue_qk();
        turn_pass(my_turn == 1 ? 3 : my_turn - 1);
        int pv_next = my_turn == 1 ? 3 : next_turn;
        wgmma_wait0();
        fence_regs(s);
        release(0);
        {
            float m0 = fmaxf(s[0], s[1]), m1 = fmaxf(s[2], s[3]), m2 = fmaxf(s[4], s[5]), m3 = fmaxf(s[6], s[7]);
#pragma unroll
            for (int i = 2; i < 16; i += 2) {
                m0 = fmaxf(m0, fmaxf(s[4 * i + 0], s[4 * i + 1]));
                m1 = fmaxf(m1, fmaxf(s[4 * i + 2], s[4 * i + 3]));
                m2 = fmaxf(m2, fmaxf(s[4 * i + 4], s[4 * i + 5]));
                m3 = fmaxf(m3, fmaxf(s[4 * i + 6], s[4 * i + 7]));
            }
            m0 = fmaxf(m0, m2); m1 = fmaxf(m1, m3);
            m0 = fmaxf(m0, __shfl_xor_sync(0xffffffffu, m0, 1));
            m1 = fmaxf(m1, __shfl_xor_sync(0xffffffffu, m1, 1));
            m0 = fmaxf(m0, __shfl_xor_sync(0xffffffffu, m0, 2));
            m1 = fmaxf(m1, __shfl_xor_sync(0xffffffffu, m1, 2));
            mc0 = -m0 * kScaleLog2e; mc1 = -m1 * kScaleLog2e;
        }
        scale_sub();
        exp_pack(0, kSplit);
#pragma unroll
        for (int i = 0; i < 64; i++) o[i] = 0.f;

#pragma unroll 1
        for (int j = 0;; j++) {
            mbar_wait(barFull + 16 * j + 8);
            turn_wait(my_turn);
            exp_pack(kSplit, 8);
            {
                const uint64_t descV = make_desc(stage, 1024, 2048);
                wgmma_fence();
#pragma unroll
                for (int k = 0; k < 8; k++)
                    wgmma_rs(o, p[4 * k + 0], p[4 * k + 1], p[4 * k + 2], p[4 * k + 3], descV + ((k * 4096) >> 4));
                wgmma_commit();
            }
            if (j == kNumBlocks - 1) {
                if (w != 1) turn_pass(2);
                break;
            }
            turn_pass(pv_next);
            pv_next = next_turn;
            wgmma_wait0();
            fence_regs(o);
            release(2 * j + 1);

            mbar_wait(barFull + 16 * j + 16);
            turn_wait(my_turn);
            issue_qk();
            turn_pass(next_turn);
            wgmma_wait0();
            fence_regs(s);
            release(2 * j + 2);
            scale_sub();
            exp_pack(0, kSplit);
        }

        l0 += l2; l1 += l3;
        l0 += __shfl_xor_sync(0xffffffffu, l0, 1);
        l1 += __shfl_xor_sync(0xffffffffu, l1, 1);
        l0 += __shfl_xor_sync(0xffffffffu, l0, 2);
        l1 += __shfl_xor_sync(0xffffffffu, l1, 2);
        float i0, i1;
        asm("rcp.approx.ftz.f32 %0, %1;" : "=f"(i0) : "f"(l0));
        asm("rcp.approx.ftz.f32 %0, %1;" : "=f"(i1) : "f"(l1));
        const bool suspicious = __any_sync(0xffffffffu, !(l0 <= 4096.f) || !(l1 <= 4096.f));
        uint32_t stA, ldA, gLo, gHi;
        asm volatile("ld.shared.v4.u32 {%0, %1, %2, %3}, [%4];" : "=r"(stA), "=r"(ldA), "=r"(gLo), "=r"(gHi) : "r"(stash) : "memory");
        uint8_t* gOt = (uint8_t*)(((uint64_t)gHi << 32) | gLo);
        if (lane == 0 && i0 != -1.f && i1 != -1.f)
            asm volatile("mbarrier.arrive.shared::cta.b64 _, [%0];" :: "r"(barDone) : "memory");
        wgmma_wait0();
        fence_regs(o);
#pragma unroll
        for (int h = 0; h < 2; h++) {
#pragma unroll
            for (int n = 4 * h; n < 4 * h + 4; n++) {
                const uint32_t x0 = pack_bf16(o[8 * n + 0] * i0, o[8 * n + 1] * i0);
                const uint32_t x1 = pack_bf16(o[8 * n + 2] * i1, o[8 * n + 3] * i1);
                const uint32_t x2 = pack_bf16(o[8 * n + 4] * i0, o[8 * n + 5] * i0);
                const uint32_t x3 = pack_bf16(o[8 * n + 6] * i1, o[8 * n + 7] * i1);
                asm volatile("stmatrix.sync.aligned.m8n8.x4.shared.b16 [%0], {%1, %2, %3, %4};"
                             :: "r"((stA ^ ((n & 3) * 32)) + h * 2048), "r"(x0), "r"(x1), "r"(x2), "r"(x3) : "memory");
            }
            __syncwarp();
#pragma unroll
            for (int i = 0; i < 4; i++) {
                uint4 v;
                asm volatile("ld.shared.v4.u32 {%0, %1, %2, %3}, [%4];" : "=r"(v.x), "=r"(v.y), "=r"(v.z), "=r"(v.w)
                             : "r"((ldA ^ ((i & 1) * 64)) + i * 512 + h * 2048) : "memory");
                asm volatile("st.global.v4.u32 [%0], {%1, %2, %3, %4};"
                             :: "l"(gOt + i * 1024 + h * 128), "r"(v.x), "r"(v.y), "r"(v.z), "r"(v.w) : "memory");
            }
        }
        if (suspicious) {
            float t0 = 0.f, t1 = 0.f;
#pragma unroll
            for (int i = 0; i < 16; i++) {
                t0 = fmaf(o[4 * i + 0], 0.f, fmaf(o[4 * i + 1], 0.f, t0));
                t1 = fmaf(o[4 * i + 2], 0.f, fmaf(o[4 * i + 3], 0.f, t1));
            }
            const uint32_t bad0 = __ballot_sync(0xffffffffu, !(l0 < 0x1p100f) || t0 != 0.f);
            const uint32_t bad1 = __ballot_sync(0xffffffffu, !(l1 < 0x1p100f) || t1 != 0.f);
            __syncwarp();
#pragma unroll 1
            for (int r = 0; r < 16; r++) {
                if ((((r < 8 ? bad0 : bad1) >> (4 * (r & 7))) & 0xF) == 0) continue;
                const size_t row = (size_t)blockIdx.x * kRowsPerCta + w * 64 + warp * 16 + r;
                exact_row(gQ + row * 256, gK + (size_t)head * (kSk * 256), gV + (size_t)head * (kSk * 256), gO + row * 256, lane);
            }
        }
    }
}

typedef CUresult (*EncodeFn)(CUtensorMap*, CUtensorMapDataType, cuuint32_t, void*, const cuuint64_t*, const cuuint64_t*,
                             const cuuint32_t*, const cuuint32_t*, CUtensorMapInterleave, CUtensorMapSwizzle,
                             CUtensorMapL2promotion, CUtensorMapFloatOOBfill);

void make_map(EncodeFn enc, CUtensorMap* map, const void* ptr, uint64_t rows) {
    cuuint64_t dims[4] = {64, 8, 2, rows / 8};
    cuuint64_t strides[3] = {256, 128, 2048};
    cuuint32_t box[4] = {64, 8, 2, 8};
    cuuint32_t estr[4] = {1, 1, 1, 1};
    enc(map, CU_TENSOR_MAP_DATA_TYPE_BFLOAT16, 4, const_cast<void*>(ptr), dims, strides, box, estr,
        CU_TENSOR_MAP_INTERLEAVE_NONE, CU_TENSOR_MAP_SWIZZLE_128B, CU_TENSOR_MAP_L2_PROMOTION_L2_256B,
        CU_TENSOR_MAP_FLOAT_OOB_FILL_NONE);
}

}

extern "C" void kernel_launch(void* const* d_in, const int* in_sizes, int n_in, void* d_out, int out_size) {
    static EncodeFn enc = nullptr;
    if (!enc) {
        void* fn = nullptr;
        cudaDriverEntryPointQueryResult st;
        cudaGetDriverEntryPoint("cuTensorMapEncodeTiled", &fn, cudaEnableDefault, &st);
        enc = (EncodeFn)fn;
        cudaFuncSetAttribute(gqa_attn_kernel, cudaFuncAttributeMaxDynamicSharedMemorySize, kSmemTotal);
    }
    CUtensorMap mq, mk, mv;
    make_map(enc, &mq, d_in[0], (uint64_t)kNumKVHeads * kRowsPerHead);
    make_map(enc, &mk, d_in[1], (uint64_t)kNumKVHeads * kSk);
    make_map(enc, &mv, d_in[2], (uint64_t)kNumKVHeads * kSk);
    gqa_attn_kernel<<<2 * kNumKVHeads, kThreads, kSmemTotal>>>(
        (const uint8_t*)d_in[0], (const uint8_t*)d_in[1], (const uint8_t*)d_in[2], (uint8_t*)d_out, mq, mk, mv);
}
```

```cpp
#include <cuda_runtime.h>
#include <cuda_bf16.h>
#include <cuda.h>
#include <stdint.h>

namespace {

constexpr int kD = 128;
constexpr int kSk = 1024;
constexpr int kRowsPerHead = 384;
constexpr int kRowsPerCta = 192;
constexpr int kNumKVHeads = 64;
constexpr int kBN = 128;
constexpr int kNumBlocks = kSk / kBN;
constexpr int kNumTiles = 2 * kNumBlocks;
constexpr int kStages = 5;
constexpr int kTileBytes = kBN * kD * 2;
constexpr int kQBytes = 64 * kD * 2;
constexpr int kSmemQ = 0;
constexpr int kSmemKV = 3 * kQBytes;
constexpr int kSmemBar = kSmemKV + kStages * kTileBytes;
constexpr int kSmemStash = kSmemBar + 256;
constexpr int kSmemTotal = kSmemStash + 384 * 16 + 1024;
constexpr int kThreads = 512;
constexpr int kSplit = 5;
constexpr float kScaleLog2e = 0.08838834764831845f * 1.4426950408889634f;

constexpr int kPace = 680;
constexpr int kLead = 430;
constexpr int kStagger = 650;
constexpr int kNumPacedTiles = 8;

__device__ __forceinline__ uint32_t smem_u32(const void* p) { return (uint32_t)__cvta_generic_to_shared(p); }
__device__ __forceinline__ uint32_t timer_ns() {
    uint32_t t; asm volatile("mov.u32 %0, %%globaltimer_lo;" : "=r"(t) :: "memory"); return t;
}

__device__ __forceinline__ void mbar_init(uint32_t bar, uint32_t count) {
    asm volatile("mbarrier.init.shared::cta.b64 [%0], %1;" :: "r"(bar), "r"(count) : "memory");
}
__device__ __forceinline__ void mbar_expect_tx(uint32_t bar, uint32_t bytes) {
    asm volatile("mbarrier.arrive.expect_tx.shared::cta.b64 _, [%0], %1;" :: "r"(bar), "r"(bytes) : "memory");
}
__device__ __forceinline__ void mbar_wait(uint32_t bar) {
    uint32_t ok;
    do {
        asm volatile("{\n\t.reg .pred p;\n\t"
                     "mbarrier.try_wait.parity.shared::cta.b64 p, [%1], 0;\n\t"
                     "selp.u32 %0, 1, 0, p;\n\t}"
                     : "=r"(ok) : "r"(bar) : "memory");
    } while (!ok);
}
__device__ __forceinline__ void mbar_wait_bounded(uint32_t bar, uint32_t tstart) {
    for (;;) {
        uint32_t ok;
        asm volatile("{\n\t.reg .pred p;\n\t"
                     "mbarrier.try_wait.parity.shared::cta.b64 p, [%1], 0, %2;\n\t"
                     "selp.u32 %0, 1, 0, p;\n\t}"
                     : "=r"(ok) : "r"(bar), "r"(1000000u) : "memory");
        if (ok) return;
        if (timer_ns() - tstart > 2000000000u) __trap();
    }
}
__device__ __forceinline__ uint32_t map_to_cta(uint32_t addr, uint32_t cta) {
    uint32_t r; asm("mapa.shared::cluster.u32 %0, %1, %2;" : "=r"(r) : "r"(addr), "r"(cta)); return r;
}
__device__ __forceinline__ void mbar_arrive_cluster(uint32_t cluster_addr) {
    asm volatile("mbarrier.arrive.shared::cluster.b64 _, [%0];" :: "r"(cluster_addr) : "memory");
}
__device__ __forceinline__ void tma_load(uint32_t dst, const CUtensorMap* map, int group, uint32_t bar) {
    asm volatile("cp.async.bulk.tensor.4d.shared::cluster.global.mbarrier::complete_tx::bytes "
                 "[%0], [%1, {%4, %4, %4, %2}], [%3];"
                 :: "r"(dst), "l"(map), "r"(group), "r"(bar), "r"(0) : "memory");
}
__device__ __forceinline__ void tma_load_mc(uint32_t dst, const CUtensorMap* map, int group, uint32_t bar, uint16_t mask) {
    asm volatile("cp.async.bulk.tensor.4d.shared::cluster.global.mbarrier::complete_tx::bytes.multicast::cluster "
                 "[%0], [%1, {%5, %5, %5, %2}], [%3], %4;"
                 :: "r"(dst), "l"(map), "r"(group), "r"(bar), "h"(mask), "r"(0) : "memory");
}
__device__ __forceinline__ void tma_store(const CUtensorMap* map, int half, int group, uint32_t src) {
    asm volatile("cp.async.bulk.tensor.4d.global.shared::cta.bulk_group [%0, {%4, %4, %1, %2}], [%3];"
                 :: "l"(map), "r"(half), "r"(group), "r"(src), "r"(0) : "memory");
}
__device__ __forceinline__ void l2_prefetch_16k(const void* p) {
    asm volatile("cp.async.bulk.prefetch.L2.global [%0], 16384;" :: "l"(p) : "memory");
}
__device__ __forceinline__ bool elect_one() {
    uint32_t p;
    asm volatile("{\n\t.reg .pred P;\n\telect.sync _|P, 0xffffffff;\n\tselp.u32 %0, 1, 0, P;\n\t}" : "=r"(p));
    return p != 0;
}
__device__ __forceinline__ void turn_wait(int id) { asm volatile("bar.sync %0, 256;" :: "r"(id) : "memory"); }
__device__ __forceinline__ void turn_pass(int id) { asm volatile("bar.arrive %0, 256;" :: "r"(id) : "memory"); }

__device__ __forceinline__ void wgmma_fence() { asm volatile("wgmma.fence.sync.aligned;" ::: "memory"); }
__device__ __forceinline__ void wgmma_commit() { asm volatile("wgmma.commit_group.sync.aligned;" ::: "memory"); }
__device__ __forceinline__ void wgmma_wait0() { asm volatile("wgmma.wait_group.sync.aligned 0;" ::: "memory"); }
__device__ __forceinline__ void wgmma_wait1() { asm volatile("wgmma.wait_group.sync.aligned 1;" ::: "memory"); }
__device__ __forceinline__ uint64_t make_desc(uint32_t addr, uint32_t lbo, uint32_t sbo) {
    return (uint64_t)((addr & 0x3FFFF) >> 4) | ((uint64_t)(lbo >> 4) << 16) | ((uint64_t)(sbo >> 4) << 32) | (1ull << 62);
}

#define ACC64(d) \
    "+f"(d[0]), "+f"(d[1]), "+f"(d[2]), "+f"(d[3]), "+f"(d[4]), "+f"(d[5]), "+f"(d[6]), "+f"(d[7]), \
    "+f"(d[8]), "+f"(d[9]), "+f"(d[10]), "+f"(d[11]), "+f"(d[12]), "+f"(d[13]), "+f"(d[14]), "+f"(d[15]), \
    "+f"(d[16]), "+f"(d[17]), "+f"(d[18]), "+f"(d[19]), "+f"(d[20]), "+f"(d[21]), "+f"(d[22]), "+f"(d[23]), \
    "+f"(d[24]), "+f"(d[25]), "+f"(d[26]), "+f"(d[27]), "+f"(d[28]), "+f"(d[29]), "+f"(d[30]), "+f"(d[31]), \
    "+f"(d[32]), "+f"(d[33]), "+f"(d[34]), "+f"(d[35]), "+f"(d[36]), "+f"(d[37]), "+f"(d[38]), "+f"(d[39]), \
    "+f"(d[40]), "+f"(d[41]), "+f"(d[42]), "+f"(d[43]), "+f"(d[44]), "+f"(d[45]), "+f"(d[46]), "+f"(d[47]), \
    "+f"(d[48]), "+f"(d[49]), "+f"(d[50]), "+f"(d[51]), "+f"(d[52]), "+f"(d[53]), "+f"(d[54]), "+f"(d[55]), \
    "+f"(d[56]), "+f"(d[57]), "+f"(d[58]), "+f"(d[59]), "+f"(d[60]), "+f"(d[61]), "+f"(d[62]), "+f"(d[63])
#define OUT64(d) \
    "=f"(d[0]), "=f"(d[1]), "=f"(d[2]), "=f"(d[3]), "=f"(d[4]), "=f"(d[5]), "=f"(d[6]), "=f"(d[7]), \
    "=f"(d[8]), "=f"(d[9]), "=f"(d[10]), "=f"(d[11]), "=f"(d[12]), "=f"(d[13]), "=f"(d[14]), "=f"(d[15]), \
    "=f"(d[16]), "=f"(d[17]), "=f"(d[18]), "=f"(d[19]), "=f"(d[20]), "=f"(d[21]), "=f"(d[22]), "=f"(d[23]), \
    "=f"(d[24]), "=f"(d[25]), "=f"(d[26]), "=f"(d[27]), "=f"(d[28]), "=f"(d[29]), "=f"(d[30]), "=f"(d[31]), \
    "=f"(d[32]), "=f"(d[33]), "=f"(d[34]), "=f"(d[35]), "=f"(d[36]), "=f"(d[37]), "=f"(d[38]), "=f"(d[39]), \
    "=f"(d[40]), "=f"(d[41]), "=f"(d[42]), "=f"(d[43]), "=f"(d[44]), "=f"(d[45]), "=f"(d[46]), "=f"(d[47]), \
    "=f"(d[48]), "=f"(d[49]), "=f"(d[50]), "=f"(d[51]), "=f"(d[52]), "=f"(d[53]), "=f"(d[54]), "=f"(d[55]), \
    "=f"(d[56]), "=f"(d[57]), "=f"(d[58]), "=f"(d[59]), "=f"(d[60]), "=f"(d[61]), "=f"(d[62]), "=f"(d[63])
#define REGS64 \
    "{%0, %1, %2, %3, %4, %5, %6, %7, %8, %9, %10, %11, %12, %13, %14, %15, " \
    "%16, %17, %18, %19, %20, %21, %22, %23, %24, %25, %26, %27, %28, %29, %30, %31, " \
    "%32, %33, %34, %35, %36, %37, %38, %39, %40, %41, %42, %43, %44, %45, %46, %47, " \
    "%48, %49, %50, %51, %52, %53, %54, %55, %56, %57, %58, %59, %60, %61, %62, %63}"

__device__ __forceinline__ void wgmma_ss(float (&d)[64], uint64_t da, uint64_t db) {
    asm volatile("wgmma.mma_async.sync.aligned.m64n128k16.f32.bf16.bf16 " REGS64 ", %64, %65, 1, 1, 1, 0, 0;"
                 : ACC64(d) : "l"(da), "l"(db));
}
__device__ __forceinline__ void wgmma_ss_init(float (&d)[64], uint64_t da, uint64_t db) {
    asm volatile("wgmma.mma_async.sync.aligned.m64n128k16.f32.bf16.bf16 " REGS64 ", %64, %65, 0, 1, 1, 0, 0;"
                 : OUT64(d) : "l"(da), "l"(db));
}
__device__ __forceinline__ void wgmma_rs(float (&d)[64], uint32_t a0, uint32_t a1, uint32_t a2, uint32_t a3, uint64_t db) {
    asm volatile("wgmma.mma_async.sync.aligned.m64n128k16.f32.bf16.bf16 " REGS64 ", {%64, %65, %66, %67}, %68, 1, 1, 1, 1;"
                 : ACC64(d) : "r"(a0), "r"(a1), "r"(a2), "r"(a3), "l"(db));
}
__device__ __forceinline__ void wgmma_rs_flag(float (&d)[64], uint32_t a0, uint32_t a1, uint32_t a2, uint32_t a3, uint64_t db,
                                              uint32_t accumulate) {
    asm volatile("{\n\t.reg .pred p;\n\tsetp.ne.u32 p, %69, 0;\n\t"
                 "wgmma.mma_async.sync.aligned.m64n128k16.f32.bf16.bf16 " REGS64 ", {%64, %65, %66, %67}, %68, p, 1, 1, 1;\n\t}"
                 : ACC64(d) : "r"(a0), "r"(a1), "r"(a2), "r"(a3), "l"(db), "r"(accumulate));
}
__device__ __forceinline__ void fence_regs(float (&d)[64]) {
#pragma unroll
    for (int i = 0; i < 64; i++) asm volatile("" : "+f"(d[i]) :: "memory");
}

__device__ __forceinline__ float ex2(float x) { float y; asm("ex2.approx.ftz.f32 %0, %1;" : "=f"(y) : "f"(x)); return y; }
__device__ __forceinline__ uint32_t pack_bf16(float lo, float hi) {
    uint32_t r; asm("cvt.rn.bf16x2.f32 %0, %1, %2;" : "=r"(r) : "f"(hi), "f"(lo)); return r;
}
__device__ __forceinline__ uint32_t or3(uint32_t a, uint32_t b, uint32_t c) {
    uint32_t r; asm("lop3.b32 %0, %1, %2, %3, 0xfe;" : "=r"(r) : "r"(a), "r"(b), "r"(c)); return r;
}
__device__ __forceinline__ float bf_lo(uint32_t v) { return __uint_as_float(v << 16); }
__device__ __forceinline__ float bf_hi(uint32_t v) { return __uint_as_float(v & 0xffff0000u); }

__device__ __forceinline__ void exact_row(const uint8_t* q, const uint8_t* k, const uint8_t* v, uint8_t* out, int lane) {
    const uint2 qq = *(const uint2*)(q + lane * 8);
    const float q0 = bf_lo(qq.x), q1 = bf_hi(qq.x), q2 = bf_lo(qq.y), q3 = bf_hi(qq.y);
    float m = -INFINITY, l = 0.f, a0 = 0.f, a1 = 0.f, a2 = 0.f, a3 = 0.f;
#pragma unroll 4
    for (int j = 0; j < kSk; j++) {
        const uint2 kk = *(const uint2*)(k + j * 256 + lane * 8);
        const uint2 vv = *(const uint2*)(v + j * 256 + lane * 8);
        float s = q0 * bf_lo(kk.x) + q1 * bf_hi(kk.x) + q2 * bf_lo(kk.y) + q3 * bf_hi(kk.y);
#pragma unroll
        for (int d = 16; d > 0; d >>= 1) s += __shfl_xor_sync(0xffffffffu, s, d);
        const float mn = (s > m || s != s) ? s : m;
        const float sc = (m == mn) ? 1.f : ex2((m - mn) * kScaleLog2e);
        const float p = (s == -INFINITY) ? 0.f : ex2((s - mn) * kScaleLog2e);
        m = mn;
        l = l * sc + p;
        a0 = a0 * sc + p * bf_lo(vv.x); a1 = a1 * sc + p * bf_hi(vv.x);
        a2 = a2 * sc + p * bf_lo(vv.y); a3 = a3 * sc + p * bf_hi(vv.y);
    }
    const float inv = 1.f / l;
    *(uint2*)(out + lane * 8) = make_uint2(pack_bf16(a0 * inv, a1 * inv), pack_bf16(a2 * inv, a3 * inv));
}

__global__ void __cluster_dims__(2, 1, 1) __launch_bounds__(kThreads, 1)
gqa_attn_kernel(const uint8_t* __restrict__ gQ, const uint8_t* __restrict__ gK, const uint8_t* __restrict__ gV,
                uint8_t* __restrict__ gO, const __grid_constant__ CUtensorMap mapQ,
                const __grid_constant__ CUtensorMap mapK, const __grid_constant__ CUtensorMap mapV,
                const __grid_constant__ CUtensorMap mapO) {
    if (threadIdx.x == 32) l2_prefetch_16k(gQ + (size_t)blockIdx.x * (3 * kQBytes));
    if (threadIdx.x == 0) {
        asm volatile("prefetch.tensormap [%0];" :: "l"(&mapQ) : "memory");
        asm volatile("prefetch.tensormap [%0];" :: "l"(&mapK) : "memory");
        asm volatile("prefetch.tensormap [%0];" :: "l"(&mapV) : "memory");
        asm volatile("prefetch.tensormap [%0];" :: "l"(&mapO) : "memory");
    }
    const int head = blockIdx.x >> 1;
    const uint32_t rank = blockIdx.x & 1;
    const uint32_t tstart = __shfl_sync(0xffffffffu, timer_ns() + (threadIdx.x & 31), 0);
    auto pace = [&](int unit) {
        const int due = unit * kPace - kLead + (kNumKVHeads - 1 - head) * kStagger / kNumKVHeads;
        for (;;) {
            const int left = due - (int)(timer_ns() - tstart);
            if (left <= 0) break;
            if (left > 64) __nanosleep(left >> 1);
        }
    };

    extern __shared__ uint8_t smem_raw[];
    const uint32_t smem = (smem_u32(smem_raw) + 1023) & ~1023u;
    const uint32_t barQ = smem + kSmemBar;
    const uint32_t barFull = barQ + 3 * 8;
    const uint32_t barEmpty = barFull + kNumTiles * 8;
    const uint32_t barDone = barEmpty + (kNumTiles - kStages) * 8;
    const int wg = __shfl_sync(0xffffffffu, threadIdx.x >> 7, 0);
    const int qgroup0 = (head * kRowsPerHead + rank * kRowsPerCta) >> 3;

    if (threadIdx.x == 0) {
#pragma unroll
        for (int i = 0; i < 3 + kNumTiles; i++) mbar_init(barQ + 8 * i, 1);
#pragma unroll
        for (int i = 0; i < kNumTiles - kStages; i++) mbar_init(barEmpty + 8 * i, i < 2 ? 6 : 4);
        mbar_init(barDone, 12);
        asm volatile("fence.mbarrier_init.release.cluster;" ::: "memory");
        asm volatile("fence.proxy.async.shared::cta;" ::: "memory");
        mbar_expect_tx(barQ, kQBytes);
        tma_load(smem + kSmemQ, &mapQ, qgroup0, barQ);
    }
    __syncwarp();
    asm volatile("barrier.cluster.arrive.relaxed.aligned;" ::: "memory");
    asm volatile("barrier.cluster.wait.aligned;" ::: "memory");

    if (wg == 0) {
        asm volatile("setmaxnreg.dec.sync.aligned.u32 32;");
        if (__shfl_sync(0xffffffffu, threadIdx.x >> 5, 0) == 0) {
            const int kvgroup0 = head * (kSk / 8) + rank * 8;
            uint32_t dst = smem + kSmemKV + rank * (kTileBytes / 2);
            auto load_tile = [&](int t, int src) {
                if (elect_one()) {
                    mbar_expect_tx(barFull + 8 * t, kTileBytes);
                    tma_load_mc(dst, (src & 1) ? &mapV : &mapK, kvgroup0 + (src >> 1) * (kBN / 8), barFull + 8 * t, (uint16_t)3);
                }
                dst += kTileBytes;
                if (dst >= smem + kSmemKV + kStages * kTileBytes) dst -= kStages * kTileBytes;
            };
            auto load_q = [&](int i) {
                if (elect_one()) {
                    mbar_expect_tx(barQ + 8 * i, kQBytes);
                    tma_load(smem + kSmemQ + i * kQBytes, &mapQ, qgroup0 + 8 * i, barQ + 8 * i);
                }
            };
            pace(1); load_tile(0, 2);
            pace(2); load_q(2);
            pace(3); load_tile(1, 0);
            pace(4); load_q(1);
            pace(5); load_tile(2, 1);
#pragma unroll 1
            for (int t = 3; t < kNumPacedTiles; t++) {
                if (t >= kStages) mbar_wait_bounded(barEmpty + 8 * (t - kStages), tstart);
                pace(t + 3);
                load_tile(t, t);
            }
#pragma unroll 1
            for (int t = kNumPacedTiles; t < kNumTiles; t++) {
                mbar_wait_bounded(barEmpty + 8 * (t - kStages), tstart);
                load_tile(t, t);
            }
            mbar_wait_bounded(barDone, tstart);
        }
    } else {
        asm volatile("setmaxnreg.inc.sync.aligned.u32 160;");
        const int w = wg - 1;
        const int lane = threadIdx.x & 31;
        const int warp = (threadIdx.x >> 5) & 3;
        const int warpU = __shfl_sync(0xffffffffu, warp, 0);
        const uint32_t sQ = smem + kSmemQ + w * kQBytes;
        const uint64_t descQ = make_desc(sQ, 16, 2048);
        const int my_turn = threadIdx.x >> 7;
        const int next_turn = my_turn == 3 ? 1 : my_turn + 1;
        const uint32_t relAddr = map_to_cta(barEmpty, lane & 1);

        const uint32_t stash = smem + kSmemStash + (threadIdx.x - 128) * 16;
        {
            const uint32_t sO = sQ + warp * 4096;
            const uint32_t stA = sO + ((lane >> 3) & 1) * 1024 + (lane & 7) * 128 + (((lane >> 4) ^ (lane & 7)) << 4);
            const uint32_t ldA = sO + (lane >> 3) * 128 + (((lane & 7) ^ (lane >> 3)) << 4);
            const uint64_t g = (uint64_t)gO + ((size_t)blockIdx.x * kRowsPerCta + w * 64 + warp * 16 + (lane >> 3)) * 256 + (lane & 7) * 16;
            asm volatile("st.shared.v4.u32 [%0], {%1, %2, %3, %4};"
                         :: "r"(stash), "r"(stA), "r"(ldA), "r"((uint32_t)g), "r"((uint32_t)(g >> 32)) : "memory");
        }

        float o[64], s[64], x[64];
        uint32_t p[32];
        float mc0, mc1;
        float l0 = 0.f, l1 = 0.f, l2 = 0.f, l3 = 0.f;
        uint32_t stage = smem + kSmemKV;

        auto issue_qk = [&](float (&acc)[64], uint32_t kaddr) {
            const uint64_t descK = make_desc(kaddr, 16, 2048);
            wgmma_fence();
#pragma unroll
            for (int k = 0; k < 8; k++) {
                const uint32_t off = ((k >> 2) * 1024 + (k & 3) * 32) >> 4;
                if (k == 0) wgmma_ss_init(acc, descQ + off, descK + off);
                else wgmma_ss(acc, descQ + off, descK + off);
            }
            wgmma_commit();
        };
        const bool rel0 = (threadIdx.x & 127) < 2;
        const bool rel = rel0 && threadIdx.x >= 256;
        auto release = [&](int t) {
            if (t + kStages < kNumTiles) { if (t < 2 ? rel0 : rel) mbar_arrive_cluster(relAddr + 8 * t); }
            stage += kTileBytes;
            if (stage == smem + kSmemKV + kStages * kTileBytes) stage = smem + kSmemKV;
        };
        auto scale_sub = [&]() {
#pragma unroll
            for (int i = 0; i < 16; i++) {
                x[4 * i + 0] = fmaf(s[4 * i + 0], kScaleLog2e, mc0);
                x[4 * i + 1] = fmaf(s[4 * i + 1], kScaleLog2e, mc0);
                x[4 * i + 2] = fmaf(s[4 * i + 2], kScaleLog2e, mc1);
                x[4 * i + 3] = fmaf(s[4 * i + 3], kScaleLog2e, mc1);
            }
        };
        auto exp_pack = [&](int k0, int k1) {
#pragma unroll
            for (int i = 2 * k0; i < 2 * k1; i++) {
                const float e0 = ex2(x[4 * i + 0]);
                const float e1 = ex2(x[4 * i + 1]);
                const float e2 = ex2(x[4 * i + 2]);
                const float e3 = ex2(x[4 * i + 3]);
                l0 += e0; l2 += e1; l1 += e2; l3 += e3;
                p[2 * i + 0] = pack_bf16(e0, e1);
                p[2 * i + 1] = pack_bf16(e2, e3);
            }
        };

        mbar_wait(barQ + 8 * w);
        mbar_wait(barFull);
        if (w == 1) turn_wait(5);
        issue_qk(s, stage);
        if (w == 1) {
            mbar_wait(barFull + 8);
            issue_qk(o, stage + kTileBytes);
            wgmma_wait1();
        } else {
            wgmma_wait0();
        }
        fence_regs(s);
        {
            float m0 = fmaxf(s[0], s[1]), m1 = fmaxf(s[2], s[3]), m2 = fmaxf(s[4], s[5]), m3 = fmaxf(s[6], s[7]);
#pragma unroll
            for (int i = 2; i < 8; i += 2) {
                m0 = fmaxf(m0, fmaxf(s[4 * i + 0], s[4 * i + 1]));
                m1 = fmaxf(m1, fmaxf(s[4 * i + 2], s[4 * i + 3]));
                m2 = fmaxf(m2, fmaxf(s[4 * i + 4], s[4 * i + 5]));
                m3 = fmaxf(m3, fmaxf(s[4 * i + 6], s[4 * i + 7]));
            }
            m0 = fmaxf(m0, m2); m1 = fmaxf(m1, m3);
            m0 = fmaxf(m0, __shfl_xor_sync(0xffffffffu, m0, 1));
            m1 = fmaxf(m1, __shfl_xor_sync(0xffffffffu, m1, 1));
            m0 = fmaxf(m0, __shfl_xor_sync(0xffffffffu, m0, 2));
            m1 = fmaxf(m1, __shfl_xor_sync(0xffffffffu, m1, 2));
            mc0 = -m0 * kScaleLog2e; mc1 = -m1 * kScaleLog2e;
        }
        scale_sub();
        exp_pack(0, kSplit);
        {
            uint32_t dep = 0;
#pragma unroll
            for (int i = 8 * kSplit; i < 64; i += 2) dep = or3(dep, __float_as_uint(x[i]), __float_as_uint(x[i + 1]));
#pragma unroll
            for (int i = 0; i < 4 * kSplit; i += 2) dep = or3(dep, p[i], p[i + 1]);
            dep = or3(or3(dep, __float_as_uint(l0), __float_as_uint(l1)), __float_as_uint(l2), __float_as_uint(l3));
            asm volatile("{\n\t.reg .pred p;\n\tsetp.ne.u32 p, %1, 0;\n\t@p mbarrier.arrive.shared::cluster.b64 _, [%0];\n\t}"
                         :: "r"(relAddr + (dep & relAddr & 7)), "r"((uint32_t)rel0) : "memory");
            stage += kTileBytes;
        }
        if (w != 1) {
            mbar_wait(barFull + 8);
            if (w == 2) turn_wait(4);
            issue_qk(o, stage);
            turn_pass(w == 0 ? 4 : 5);
        }
        wgmma_wait0();
        fence_regs(o);
        release(1);
        uint32_t p0[32];
#pragma unroll
        for (int i = 0; i < 16; i++) {
            const float e0 = ex2(fmaf(o[4 * i + 0], kScaleLog2e, mc0));
            const float e1 = ex2(fmaf(o[4 * i + 1], kScaleLog2e, mc0));
            const float e2 = ex2(fmaf(o[4 * i + 2], kScaleLog2e, mc1));
            const float e3 = ex2(fmaf(o[4 * i + 3], kScaleLog2e, mc1));
            l0 += e0; l2 += e1; l1 += e2; l3 += e3;
            p0[2 * i + 0] = pack_bf16(e0, e1);
            p0[2 * i + 1] = pack_bf16(e2, e3);
        }
        {
            uint32_t dep = 0;
#pragma unroll
            for (int i = 0; i < 32; i += 2) dep = or3(dep, p0[i], p0[i + 1]);
            dep = or3(or3(dep, __float_as_uint(l0), __float_as_uint(l1)), __float_as_uint(l2), __float_as_uint(l3));
            mbar_wait(barFull + 16 + __shfl_sync(0xffffffffu, dep & relAddr & 7, 0));
        }
        if (w != 0) turn_wait(my_turn);
        {
            const uint64_t descV = make_desc(stage, 1024, 2048);
            wgmma_fence();
            wgmma_rs_flag(o, p0[0], p0[1], p0[2], p0[3], descV, gridDim.y - 1  );
#pragma unroll
            for (int k = 1; k < 8; k++)
                wgmma_rs(o, p0[4 * k + 0], p0[4 * k + 1], p0[4 * k + 2], p0[4 * k + 3], descV + ((k * 4096) >> 4));
            wgmma_commit();
        }
        turn_pass(my_turn == 1 ? 3 : 1);
        int pv_next = my_turn == 3 ? 2 : 3;
        wgmma_wait0();
        fence_regs(o);
        release(2);

#pragma unroll 1
        for (int j = 1;; j++) {
            mbar_wait(barFull + 16 * j + 8);
            turn_wait(my_turn);
            exp_pack(kSplit, 8);
            {
                const uint64_t descV = make_desc(stage, 1024, 2048);
                wgmma_fence();
#pragma unroll
                for (int k = 0; k < 8; k++)
                    wgmma_rs(o, p[4 * k + 0], p[4 * k + 1], p[4 * k + 2], p[4 * k + 3], descV + ((k * 4096) >> 4));
                wgmma_commit();
            }
            if (j == kNumBlocks - 1) {
                if (w != 1) turn_pass(2);
                break;
            }
            turn_pass(pv_next);
            pv_next = next_turn;
            wgmma_wait0();
            fence_regs(o);
            release(2 * j + 1);

            mbar_wait(barFull + 16 * j + 16);
            turn_wait(my_turn);
            issue_qk(s, stage);
            turn_pass(next_turn);
            wgmma_wait0();
            fence_regs(s);
            release(2 * j + 2);
            scale_sub();
            exp_pack(0, kSplit);
        }

        l0 += l2; l1 += l3;
        l0 += __shfl_xor_sync(0xffffffffu, l0, 1);
        l1 += __shfl_xor_sync(0xffffffffu, l1, 1);
        l0 += __shfl_xor_sync(0xffffffffu, l0, 2);
        l1 += __shfl_xor_sync(0xffffffffu, l1, 2);
        float i0, i1;
        asm("rcp.approx.ftz.f32 %0, %1;" : "=f"(i0) : "f"(l0));
        asm("rcp.approx.ftz.f32 %0, %1;" : "=f"(i1) : "f"(l1));
        const bool suspicious = __any_sync(0xffffffffu, !(l0 >= 0.5f && l0 <= 4096.f && l1 >= 0.5f && l1 <= 4096.f));
        uint32_t stA, ldA, gLo, gHi;
        asm volatile("ld.shared.v4.u32 {%0, %1, %2, %3}, [%4];" : "=r"(stA), "=r"(ldA), "=r"(gLo), "=r"(gHi) : "r"(stash) : "memory");
        uint8_t* gOt = (uint8_t*)(((uint64_t)gHi << 32) | gLo);
        if (lane == 0 && i0 != -1.f && i1 != -1.f)
            asm volatile("mbarrier.arrive.shared::cta.b64 _, [%0];" :: "r"(barDone) : "memory");
        wgmma_wait0();
        fence_regs(o);
        const bool leader = elect_one();
#pragma unroll
        for (int h = 0; h < 2; h++) {
#pragma unroll
            for (int n = 4 * h; n < 4 * h + 4; n++) {
                const uint32_t x0 = pack_bf16(o[8 * n + 0] * i0, o[8 * n + 1] * i0);
                const uint32_t x1 = pack_bf16(o[8 * n + 2] * i1, o[8 * n + 3] * i1);
                const uint32_t x2 = pack_bf16(o[8 * n + 4] * i0, o[8 * n + 5] * i0);
                const uint32_t x3 = pack_bf16(o[8 * n + 6] * i1, o[8 * n + 7] * i1);
                asm volatile("stmatrix.sync.aligned.m8n8.x4.shared.b16 [%0], {%1, %2, %3, %4};"
                             :: "r"((stA ^ ((n & 3) * 32)) + h * 2048), "r"(x0), "r"(x1), "r"(x2), "r"(x3) : "memory");
            }
            if (w != 1) {
                asm volatile("fence.proxy.async.shared::cta;" ::: "memory");
                __syncwarp();
                if (leader) {
                    tma_store(&mapO, h, qgroup0 + w * 8 + warpU * 2, sQ + warpU * 4096 + h * 2048);
                    if (h == 1) {
                        asm volatile("cp.async.bulk.commit_group;" ::: "memory");
                        asm volatile("cp.async.bulk.wait_group 0;" ::: "memory");
                    }
                }
                continue;
            }
            __syncwarp();
#pragma unroll
            for (int i = 0; i < 4; i++) {
                uint4 v;
                asm volatile("ld.shared.v4.u32 {%0, %1, %2, %3}, [%4];" : "=r"(v.x), "=r"(v.y), "=r"(v.z), "=r"(v.w)
                             : "r"((ldA ^ ((i & 1) * 64)) + i * 512 + h * 2048) : "memory");
                asm volatile("st.global.v4.u32 [%0], {%1, %2, %3, %4};"
                             :: "l"(gOt + i * 1024 + h * 128), "r"(v.x), "r"(v.y), "r"(v.z), "r"(v.w) : "memory");
            }
        }
        if (suspicious) {
            float t0 = 0.f, t1 = 0.f;
#pragma unroll
            for (int i = 0; i < 16; i++) {
                t0 = fmaf(o[4 * i + 0], 0.f, fmaf(o[4 * i + 1], 0.f, t0));
                t1 = fmaf(o[4 * i + 2], 0.f, fmaf(o[4 * i + 3], 0.f, t1));
            }
            const uint32_t bad0 = __ballot_sync(0xffffffffu, !(l0 >= 0.5f && l0 < 0x1p100f) || t0 != 0.f);
            const uint32_t bad1 = __ballot_sync(0xffffffffu, !(l1 >= 0.5f && l1 < 0x1p100f) || t1 != 0.f);
            __syncwarp();
#pragma unroll 1
            for (int r = 0; r < 16; r++) {
                if ((((r < 8 ? bad0 : bad1) >> (4 * (r & 7))) & 0xF) == 0) continue;
                const size_t row = (size_t)blockIdx.x * kRowsPerCta + w * 64 + warp * 16 + r;
                exact_row(gQ + row * 256, gK + (size_t)head * (kSk * 256), gV + (size_t)head * (kSk * 256), gO + row * 256, lane);
            }
        }
    }
}

typedef CUresult (*EncodeFn)(CUtensorMap*, CUtensorMapDataType, cuuint32_t, void*, const cuuint64_t*, const cuuint64_t*,
                             const cuuint32_t*, const cuuint32_t*, CUtensorMapInterleave, CUtensorMapSwizzle,
                             CUtensorMapL2promotion, CUtensorMapFloatOOBfill);

void make_map(EncodeFn enc, CUtensorMap* map, const void* ptr, uint64_t rows, uint32_t box_halves, uint32_t box_groups) {
    cuuint64_t dims[4] = {64, 8, 2, rows / 8};
    cuuint64_t strides[3] = {256, 128, 2048};
    cuuint32_t box[4] = {64, 8, box_halves, box_groups};
    cuuint32_t estr[4] = {1, 1, 1, 1};
    enc(map, CU_TENSOR_MAP_DATA_TYPE_BFLOAT16, 4, const_cast<void*>(ptr), dims, strides, box, estr,
        CU_TENSOR_MAP_INTERLEAVE_NONE, CU_TENSOR_MAP_SWIZZLE_128B, CU_TENSOR_MAP_L2_PROMOTION_L2_256B,
        CU_TENSOR_MAP_FLOAT_OOB_FILL_NONE);
}

}

extern "C" void kernel_launch(void* const* d_in, const int* in_sizes, int n_in, void* d_out, int out_size) {
    static EncodeFn enc = nullptr;
    if (!enc) {
        void* fn = nullptr;
        cudaDriverEntryPointQueryResult st;
        cudaGetDriverEntryPoint("cuTensorMapEncodeTiled", &fn, cudaEnableDefault, &st);
        enc = (EncodeFn)fn;
        cudaFuncSetAttribute(gqa_attn_kernel, cudaFuncAttributeMaxDynamicSharedMemorySize, kSmemTotal);
    }
    CUtensorMap mq, mk, mv, mo;
    make_map(enc, &mq, d_in[0], (uint64_t)kNumKVHeads * kRowsPerHead, 2, 8);
    make_map(enc, &mk, d_in[1], (uint64_t)kNumKVHeads * kSk, 2, 8);
    make_map(enc, &mv, d_in[2], (uint64_t)kNumKVHeads * kSk, 2, 8);
    make_map(enc, &mo, d_out, (uint64_t)kNumKVHeads * kRowsPerHead, 1, 2);
    gqa_attn_kernel<<<2 * kNumKVHeads, kThreads, kSmemTotal>>>(
        (const uint8_t*)d_in[0], (const uint8_t*)d_in[1], (const uint8_t*)d_in[2], (uint8_t*)d_out, mq, mk, mv, mo);
}
```
